```python
import torch

def _softmax(x, axis=-1):
    return torch.softmax(x, dim=axis)
def _gelu(x):
    return torch.nn.functional.gelu(x, approximate="tanh")
def _silu(x):
    return torch.nn.functional.silu(x)
def _sigmoid(x):
    return torch.sigmoid(x)
def _layernorm(x, axis=-1, eps=1e-5):
    m = x.mean(dim=axis, keepdim=True)
    v = x.var(dim=axis, keepdim=True, unbiased=False)
    return (x - m) / torch.sqrt(v + eps)
def _scatter_add(tgt, idx, src, axis=0):
    return tgt.clone().index_add_(axis, idx, src)
def _segment_sum(src, seg, n):
    out = torch.zeros((n,) + src.shape[1:], dtype=src.dtype)
    return out.index_add_(0, seg, src)
def _pad(x, pw):
    flat = tuple(v for pair in reversed(pw) for v in pair)
    return torch.nn.functional.pad(x, flat)

kernel_name = 'sequential_preLN__sliding_block_cached__moe_arch_mod__decode'

def setup_inputs():

    _w = (lambda a: (lambda t: t.to(torch.bfloat16) if t.is_floating_point() else t)(torch.as_tensor(a)))
    def _A_setup():
        B, Sq, D = 2, 1, 512
        Hq, Hkv, Sk, Dh = 32, 32, 16384, 128
        assert Hq % Hkv == 0, (Hq, Hkv)
        return {
            "x": _w((lambda *s: torch.randn(*s, dtype=torch.bfloat16) * 0.05)(B, Sq, D)),
            "k_cache": _w((lambda *s: torch.randn(*s, dtype=torch.bfloat16) * 3.2)(B, Hkv, Sk, Dh)),
            "v_cache": _w((lambda *s: torch.randn(*s, dtype=torch.bfloat16) * 0.4)(B, Hkv, Sk, Dh)),
            "wq": _w((lambda *s: torch.randn(*s, dtype=torch.bfloat16) * 3.2)(D, Hq * Dh) * (D ** -0.5)),
            "wo": _w((lambda *s: torch.randn(*s, dtype=torch.bfloat16) * 0.4)(Hq * Dh, D) * ((Hq * Dh) ** -0.5)),
        }
    _A_in = _A_setup()

    def _B_setup():
        B, S, D, F, C = 2, 1, 512, 1376, 1
        return {
            "x": _w((lambda *s: torch.randn(*s, dtype=torch.bfloat16) * 0.05)(B, S, D)),
            "w_r": _w((lambda *s: torch.randn(*s, dtype=torch.bfloat16) * 3.2)(D)),
            "w_gate": _w((lambda *s: torch.randn(*s, dtype=torch.bfloat16) * 0.1)(D, F)),
            "w_up": _w((lambda *s: torch.randn(*s, dtype=torch.bfloat16) * 0.1)(D, F)),
            "w_down": _w((lambda *s: torch.randn(*s, dtype=torch.bfloat16) * 0.1)(F, D)),
        }
    _B_in = _B_setup()

    return {
        "A_x": _A_in["x"],
        "A_k_cache": _A_in["k_cache"],
        "A_v_cache": _A_in["v_cache"],
        "A_wq": _A_in["wq"],
        "A_wo": _A_in["wo"],
        "B_x": _B_in["x"],
        "B_w_r": _B_in["w_r"],
        "B_w_gate": _B_in["w_gate"],
        "B_w_up": _B_in["w_up"],
        "B_w_down": _B_in["w_down"],
    }

def reference(A_x, A_k_cache, A_v_cache, A_wq, A_wo, B_x, B_w_r, B_w_gate, B_w_up, B_w_down):
    def _A_ref(x, k_cache, v_cache, wq, wo):
        B, Sq, D = x.shape
        Hq, Dh = 32, 128
        Hkv, Sk = k_cache.shape[1], k_cache.shape[2]
        W = min(4096, max(256, Sk // 4))
        rep = Hq // Hkv
        q = (lambda x, *d: x.permute(*d))((x @ wq).reshape(B, Sq, Hq, Dh), 0, 2, 1, 3)
        k = (lambda x, n, axis: torch.repeat_interleave(x, n, dim=axis))(k_cache[:, :, Sk - W:, :], rep, axis=1)
        v = (lambda x, n, axis: torch.repeat_interleave(x, n, dim=axis))(v_cache[:, :, Sk - W:, :], rep, axis=1)
        scores = torch.einsum("bhqd,bhkd->bhqk", q, k) * (Dh ** -0.5)
        p = _softmax(scores, axis=-1)
        o = torch.einsum("bhqk,bhkd->bhqd", p, v)
        return (lambda x, *d: x.permute(*d))(o, 0, 2, 1, 3).reshape(B, Sq, Hq * Dh) @ wo

    def _B_ref(x, w_r, w_gate, w_up, w_down):
        B, S, D = x.shape
        C = 1
        r = x @ w_r
        idx = torch.argsort(-r, axis=-1)[:, :C]
        idx_e = (lambda x, n, axis: torch.repeat_interleave(x, n, dim=axis))(idx.reshape(B, C, 1), D, axis=2)
        x_sel = (lambda x, i, axis: torch.take_along_dim(x, i, dim=axis))(x, idx_e, axis=1)
        g = _silu(x_sel @ w_gate)
        u = x_sel @ w_up
        y = (g * u) @ w_down
        r_sel = _sigmoid((lambda x, i, axis: torch.take_along_dim(x, i, dim=axis))(r, idx, axis=1))
        y = y * r_sel.reshape(B, C, 1)
        b_off = (torch.arange(B) * S).reshape(B, 1)
        flat_idx = (idx + b_off).reshape(B * C)
        zero = (x * 0.0).reshape(B * S, D)
        upd = _scatter_add(zero, flat_idx, y.reshape(B * C, D), axis=0)
        return x + upd.reshape(B, S, D)

    x = A_x
    h = x + _A_ref(_layernorm(x, axis=-1), A_k_cache, A_v_cache, A_wq, A_wo)
    h2 = h + _B_ref(_layernorm(h, axis=-1), B_w_r, B_w_gate, B_w_up, B_w_down)
    return h2
```

```cpp
#include <cuda_runtime.h>
#include <cuda.h>
#include <cuda_bf16.h>
#include <stdint.h>

namespace {

constexpr int DH = 128;
constexpr int SK = 16384;
constexpr int WIN = 4096;
constexpr int FF = 1376;
constexpr int NCTA = 128;
constexpr int NTHREADS = 512;
constexpr int TILE_BYTES = 32768;
constexpr int NTILES = 16;
#define NSTAGES 4
#define DEPTH 2
#define INIT_TILES 3
#define WO_POS 14
#define GU_POS 16
#define HINT_SLACK 4
static_assert(WO_POS <= GU_POS && GU_POS <= 16 && DEPTH < NSTAGES && INIT_TILES >= DEPTH && INIT_TILES >= 2 && INIT_TILES <= NSTAGES, "bad stream order");
static_assert(NSTAGES >= 4 || (NSTAGES == 3 && GU_POS > WO_POS), "parity hazard");
constexpr bool WO_LATE = WO_POS + NSTAGES >= 20;
constexpr int N_K0 = 2, N_V0 = 18;
constexpr int N_WO = N_V0 + WO_POS;
constexpr int N_GU = N_V0 + 2 + GU_POS;
constexpr int N_DN = 37, N_TOT = 38;
constexpr int NFFN = FF / 16;
constexpr unsigned SPIN_LIMIT = 1u << 22;

constexpr int SM_RING = 0;
constexpr int SM_R = SM_RING + NSTAGES * TILE_BYTES;
constexpr int SM_S = SM_R + 32 * 136 * 4;
constexpr int SM_P = SM_S + 8192;
constexpr int SM_HBF = SM_P + 4096;
constexpr int SM_QS = SM_HBF + 2048;
constexpr int SM_OBF = SM_QS + 256;
constexpr int SM_ML = SM_OBF + 256;
constexpr int SM_F = SM_ML + 64;
constexpr int SM_YR = SM_F + 32;
constexpr int SM_EPOCH = SM_YR + 8 * 128;
constexpr int SM_QP = SM_EPOCH + 32;
constexpr int SM_OX = SM_QP + 512;
constexpr int SM_MLX = SM_OX + 512;
constexpr int SM_WR = SM_MLX + 16;
constexpr int SM_X = SM_WR + 1024;
constexpr int SM_BAR = SM_X + 2048;
constexpr int SM_TOTAL = SM_BAR + 8 * (2 * NSTAGES + 8);

struct Scratch {
    float2 hacc[2][1024];
    uint32_t yx[2][NFFN * 1024];
    unsigned counter[8 * 32];
    unsigned epoch[32];
};
__device__ __align__(128) Scratch g_scratch;

__device__ __forceinline__ uint32_t smem_u32(const void* p) { return (uint32_t)__cvta_generic_to_shared(p); }
__device__ __forceinline__ void mbar_init(uint32_t bar, uint32_t cnt) {
    asm volatile("mbarrier.init.shared::cta.b64 [%0], %1;" ::"r"(bar), "r"(cnt) : "memory");
}
__device__ __forceinline__ void mbar_expect_tx(uint32_t bar, uint32_t bytes) {
    asm volatile("mbarrier.arrive.expect_tx.shared::cta.b64 _, [%0], %1;" ::"r"(bar), "r"(bytes) : "memory");
}
__device__ __forceinline__ void mbar_arrive(uint32_t bar) {
    asm volatile("mbarrier.arrive.shared::cta.b64 _, [%0];" ::"r"(bar) : "memory");
}
__device__ __forceinline__ bool mbar_try(uint32_t bar, uint32_t parity) {
    uint32_t ok;
    asm volatile(
        "{\n.reg .pred p;\n"
        "mbarrier.try_wait.parity.shared::cta.b64 p, [%1], %2;\n"
        "selp.u32 %0, 1, 0, p;\n}"
        : "=r"(ok)
        : "r"(bar), "r"(parity)
        : "memory");
    return ok != 0;
}
__device__ __forceinline__ void mbar_wait(uint32_t bar, uint32_t parity) {
    unsigned n = 0;
    while (!mbar_try(bar, parity)) {
        if (++n > SPIN_LIMIT) __trap();
    }
}
__device__ __forceinline__ void bulk_load(uint32_t dst, const void* src, uint32_t bytes, uint32_t bar, uint64_t pol) {
    asm volatile(
        "cp.async.bulk.shared::cluster.global.mbarrier::complete_tx::bytes.L2::cache_hint [%0], [%1], %2, [%3], %4;" ::"r"(dst),
        "l"(src), "r"(bytes), "r"(bar), "l"(pol)
        : "memory");
}
__device__ __forceinline__ void tma_2d(uint32_t dst, const CUtensorMap* tm, int c0, int c1, uint32_t bar) {
    asm volatile("cp.async.bulk.tensor.2d.shared::cluster.global.mbarrier::complete_tx::bytes [%0], [%1, {%3, %4}], [%2];" ::"r"(dst),
                 "l"(tm), "r"(bar), "r"(c0), "r"(c1)
                 : "memory");
}
__device__ __forceinline__ void tma_4d(uint32_t dst, const CUtensorMap* tm, int c0, int c1, int c2, int c3, uint32_t bar) {
    asm volatile(
        "cp.async.bulk.tensor.4d.shared::cluster.global.mbarrier::complete_tx::bytes [%0], [%1, {%3, %4, %5, %6}], [%2];" ::"r"(dst),
        "l"(tm), "r"(bar), "r"(c0), "r"(c1), "r"(c2), "r"(c3)
        : "memory");
}
__device__ __forceinline__ void tma_5d0(uint32_t dst, const CUtensorMap* tm, int c0, uint32_t bar) {
    asm volatile(
        "cp.async.bulk.tensor.5d.shared::cluster.global.mbarrier::complete_tx::bytes [%0], [%1, {%3, %4, %4, %4, %4}], [%2];" ::"r"(dst),
        "l"(tm), "r"(bar), "r"(c0), "r"(0)
        : "memory");
}
__device__ __forceinline__ uint32_t mapa(uint32_t a, uint32_t rank) {
    uint32_t r;
    asm("mapa.shared::cluster.u32 %0, %1, %2;" : "=r"(r) : "r"(a), "r"(rank));
    return r;
}
__device__ __forceinline__ void st_async_f32(uint32_t ra, float v, uint32_t rbar) {
    asm volatile("st.async.weak.shared::cluster.mbarrier::complete_tx::bytes.f32 [%0], %1, [%2];" ::"r"(ra), "f"(v), "r"(rbar)
                 : "memory");
}
__device__ __forceinline__ void bar_sync(int id, int n) { asm volatile("bar.sync %0, %1;" ::"r"(id), "r"(n) : "memory"); }
__device__ __forceinline__ void bar_arrive(int id, int n) { asm volatile("bar.arrive %0, %1;" ::"r"(id), "r"(n) : "memory"); }

__device__ __forceinline__ uint4 lds128(uint32_t a) {
    uint4 v;
    asm volatile("ld.shared.v4.u32 {%0,%1,%2,%3}, [%4];" : "=r"(v.x), "=r"(v.y), "=r"(v.z), "=r"(v.w) : "r"(a) : "memory");
    return v;
}
__device__ __forceinline__ uint2 lds64(uint32_t a) {
    uint2 v;
    asm volatile("ld.shared.v2.u32 {%0,%1}, [%2];" : "=r"(v.x), "=r"(v.y) : "r"(a) : "memory");
    return v;
}
__device__ __forceinline__ uint32_t lds32(uint32_t a) {
    uint32_t v;
    asm volatile("ld.shared.u32 %0, [%1];" : "=r"(v) : "r"(a) : "memory");
    return v;
}
__device__ __forceinline__ uint4 ldg128(const void* p) {
    uint4 v;
    asm volatile("ld.global.v4.u32 {%0,%1,%2,%3}, [%4];" : "=r"(v.x), "=r"(v.y), "=r"(v.z), "=r"(v.w) : "l"(p) : "memory");
    return v;
}
__device__ __forceinline__ uint32_t ldg16(const void* p) {
    uint16_t v;
    asm volatile("ld.global.u16 %0, [%1];" : "=h"(v) : "l"(p) : "memory");
    return v;
}
__device__ __forceinline__ void mma16816(float (&c)[4], uint32_t a0, uint32_t a1, uint32_t a2, uint32_t a3, uint32_t b0,
                                         uint32_t b1) {
    asm volatile(
        "mma.sync.aligned.m16n8k16.row.col.f32.bf16.bf16.f32 {%0,%1,%2,%3}, {%4,%5,%6,%7}, {%8,%9}, {%0,%1,%2,%3};"
        : "+f"(c[0]), "+f"(c[1]), "+f"(c[2]), "+f"(c[3])
        : "r"(a0), "r"(a1), "r"(a2), "r"(a3), "r"(b0), "r"(b1));
}
__device__ __forceinline__ float bf_lo(uint32_t w) { return __uint_as_float(w << 16); }
__device__ __forceinline__ float bf_hi(uint32_t w) { return __uint_as_float(w & 0xffff0000u); }
__device__ __forceinline__ uint32_t pack_bf16(float lo, float hi) {
    uint32_t r;
    asm("cvt.rn.bf16x2.f32 %0, %1, %2;" : "=r"(r) : "f"(hi), "f"(lo));
    return r;
}
__device__ __forceinline__ float bf_round(float x) { return __uint_as_float(pack_bf16(0.f, x)); }
__device__ __forceinline__ float rcp_fast(float x) {
    float r;
    asm("rcp.approx.ftz.f32 %0, %1;" : "=f"(r) : "f"(x));
    return r;
}
__device__ __forceinline__ void ln_scalars(float mean, float var, float& mu, float& den) {
    mu = bf_round(mean);
    float sq;
    asm("sqrt.approx.f32 %0, %1;" : "=f"(sq) : "f"(bf_round(bf_round(var) + 1e-5f)));
    den = bf_round(sq);
}
__device__ __forceinline__ void st_gpu128(void* p, uint32_t a, uint32_t b, uint32_t c, uint32_t d) {
    asm volatile("st.relaxed.gpu.global.v4.u32 [%0], {%1, %2, %3, %4};" ::"l"(p), "r"(a), "r"(b), "r"(c), "r"(d) : "memory");
}
__device__ __forceinline__ uint4 ld_gpu128(const void* p) {
    uint4 v;
    asm volatile("ld.relaxed.gpu.global.v4.u32 {%0, %1, %2, %3}, [%4];" : "=r"(v.x), "=r"(v.y), "=r"(v.z), "=r"(v.w) : "l"(p) : "memory");
    return v;
}
__device__ __forceinline__ uint32_t nz_bits(float v) {
    const uint32_t u = __float_as_uint(v);
    return u ? u : 0x80000000u;
}
__device__ __forceinline__ float warp_sum(float v) {
#pragma unroll
    for (int o = 16; o > 0; o >>= 1) v += __shfl_xor_sync(0xffffffffu, v, o);
    return v;
}
__device__ __forceinline__ unsigned ld_epoch(const unsigned char* smem) {
    return *reinterpret_cast<const volatile unsigned*>(smem + SM_EPOCH);
}

__device__ __forceinline__ void weighted_rows(float (&acc)[4][4], uint32_t a0, uint2 pw, uint32_t s0, uint32_t s1) {
#pragma unroll
    for (int grp = 0; grp < 2; grp++) {
        const uint32_t w = grp ? pw.y : pw.x;
        const uint32_t b0 = __byte_perm(w, 0, s0), b1 = __byte_perm(w, 0, s1);
        const uint4 v0 = lds128(a0 + grp * 256);
        const uint4 v1 = lds128(a0 + grp * 256 + 128);
        const uint4 v2 = lds128(a0 + grp * 256 + 2048);
        const uint4 v3 = lds128(a0 + grp * 256 + 2048 + 128);
        mma16816(acc[0], v0.x, v1.x, v2.x, v3.x, b0, b1);
        mma16816(acc[1], v0.y, v1.y, v2.y, v3.y, b0, b1);
        mma16816(acc[2], v0.z, v1.z, v2.z, v3.z, b0, b1);
        mma16816(acc[3], v0.w, v1.w, v2.w, v3.w, b0, b1);
    }
}

__global__ void __cluster_dims__(2, 1, 1) __launch_bounds__(NTHREADS, 1)
fused_decode_kernel(const __grid_constant__ CUtensorMap tm_wq, const __grid_constant__ CUtensorMap tm_wo,
                    const __grid_constant__ CUtensorMap tm_gate, const __grid_constant__ CUtensorMap tm_up,
                    const __nv_bfloat16* __restrict__ x, const __nv_bfloat16* __restrict__ kc,
                    const __nv_bfloat16* __restrict__ vc, const __nv_bfloat16* __restrict__ w_r,
                    const __nv_bfloat16* __restrict__ w_down, __nv_bfloat16* __restrict__ out, Scratch* __restrict__ sc) {
    extern __shared__ __align__(1024) unsigned char smem[];
    const uint32_t sb = smem_u32(smem);
    const int tid = threadIdx.x, warp = tid >> 5, lane = tid & 31;
    const int g = lane >> 2, t = lane & 3;
    const int cta = blockIdx.x;
    const int h = cta >> 2, b = (cta >> 1) & 1, s = cta & 1;
    const bool ffn = cta < NFFN;
    const uint32_t bar_full = sb + SM_BAR, bar_empty = bar_full + 8 * NSTAGES;
    const uint32_t bar_ml = bar_empty + 8 * NSTAGES, bar_q = bar_ml + 8, bar_mlx = bar_q + 8, bar_ox = bar_mlx + 8;
    const uint32_t bar_wo = bar_ox + 8, bar_gu = bar_wo + 8, bar_dn = bar_gu + 8;

    const size_t kv_off = ((size_t)(b * 32 + h) * SK + (SK - WIN) + (size_t)s * 128) * DH;
    constexpr int TSTRIDE = 2 * TILE_BYTES;
    const char* kbase = reinterpret_cast<const char*>(kc + kv_off);
    uint64_t pol;
    asm volatile("createpolicy.fractional.L2::evict_first.b64 %0, 1.0;" : "=l"(pol));

    if (tid == 256) {
#pragma unroll
        for (int i = 0; i < NSTAGES; i++) mbar_init(bar_full + 8 * i, 1);
        asm volatile("fence.proxy.async.shared::cta;" ::: "memory");
#pragma unroll
        for (int i = 0; i < 2; i++) {
            mbar_expect_tx(bar_full + 8 * i, TILE_BYTES);
            tma_2d(sb + SM_RING + i * TILE_BYTES, &tm_wq, h * 128, 256 * s + 128 * i, bar_full + 8 * i);
        }
#pragma unroll
        for (int i = 2; i < INIT_TILES; i++) {
            mbar_expect_tx(bar_full + 8 * i, TILE_BYTES);
            bulk_load(sb + SM_RING + i * TILE_BYTES, kbase + (size_t)(i - 2) * TSTRIDE, TILE_BYTES, bar_full + 8 * i, pol);
        }
#pragma unroll
        for (int i = 0; i < NSTAGES; i++) mbar_init(bar_empty + 8 * i, 8);
        mbar_init(bar_ml, 8);
#pragma unroll
        for (int i = 0; i < 6; i++) mbar_init(bar_q + 8 * i, 1);
        asm volatile("fence.mbarrier_init.release.cluster;" ::: "memory");
        asm volatile("fence.proxy.async.shared::cta;" ::: "memory");
        mbar_expect_tx(bar_q, 512);
        mbar_expect_tx(bar_mlx, 8);
        mbar_expect_tx(bar_ox, 512);
        mbar_expect_tx(bar_wo, 2 * TILE_BYTES);
        mbar_expect_tx(bar_gu, TILE_BYTES);
        mbar_expect_tx(bar_dn, TILE_BYTES / 2);
    }
    __syncwarp();
    asm volatile("barrier.cluster.arrive.relaxed.aligned;" ::: "memory");
    const uint32_t sel_lo_e = (g & 1) ? 0x1044u : 0x4410u;
    const uint32_t sel_hi_e = (g & 1) ? 0x3244u : 0x4432u;

    auto o_merge = [&]() {
        bar_sync(0, NTHREADS);
        const int d = tid >> 2, part = tid & 3;
        const float* r = reinterpret_cast<const float*>(smem + SM_R) + part * 136 + d;
        const float4 f0 = reinterpret_cast<const float4*>(smem + SM_F)[0];
        const float4 f1 = reinterpret_cast<const float4*>(smem + SM_F)[1];
        float o = r[0] * f0.x;
        o = fmaf(r[544], f0.y, o);
        o = fmaf(r[2 * 544], f0.z, o);
        o = fmaf(r[3 * 544], f0.w, o);
        float o2 = r[4 * 544] * f1.x;
        o2 = fmaf(r[5 * 544], f1.y, o2);
        o2 = fmaf(r[6 * 544], f1.z, o2);
        o2 = fmaf(r[7 * 544], f1.w, o2);
        o += o2;
        o += __shfl_xor_sync(0xffffffffu, o, 1);
        o += __shfl_xor_sync(0xffffffffu, o, 2);
        if (part == 0) st_async_f32(mapa(sb + SM_OX + d * 4, s ^ 1), o, mapa(bar_ox, s ^ 1));
        mbar_wait(bar_ox, 0);
        if (part == 0) {
            o += reinterpret_cast<const float*>(smem + SM_OX)[d];
            reinterpret_cast<__nv_bfloat16*>(smem + SM_OBF)[d] = __float2bfloat16_rn(o);
        }
    };

    if (warp < 8) {
        const bool active = (g >> 1) == t;
        const uint32_t ds0 = active ? sel_lo_e : 0x4444u, ds1 = active ? sel_hi_e : 0x4444u;
        const int ch = (g + 2 * t) & 7;
        const uint32_t voff = sb + SM_RING + (16 * warp + 2 * t) * 256 + ch * 16;
        float4* rrow = reinterpret_cast<float4*>(smem + SM_R + ((warp * 4 + t) * 136 + 8 * ch) * 4);
        float acc[4][4] = {};
        auto store_rows = [&]() {
            rrow[0] = make_float4(acc[0][0], acc[0][1], acc[1][0], acc[1][1]);
            rrow[1] = make_float4(acc[2][0], acc[2][1], acc[3][0], acc[3][1]);
            rrow[16] = make_float4(acc[0][2], acc[0][3], acc[1][2], acc[1][3]);
            rrow[17] = make_float4(acc[2][2], acc[2][3], acc[3][2], acc[3][3]);
        };
        {
            const uint4 xv0 = ldg128(x + b * 512 + lane * 16), xv1 = ldg128(x + b * 512 + lane * 16 + 8);
            const uint32_t xk = ldg16(x + b * 512 + 256 * s + 128 * (lane >> 4) + 16 * warp + (lane & 15));
            const uint32_t w[8] = {xv0.x, xv0.y, xv0.z, xv0.w, xv1.x, xv1.y, xv1.z, xv1.w};
            float sum = 0.f;
#pragma unroll
            for (int i = 0; i < 8; i++) sum += bf_lo(w[i]) + bf_hi(w[i]);
            const float mu = warp_sum(sum) * (1.f / 512.f);
            float sq = 0.f;
#pragma unroll
            for (int i = 0; i < 8; i++) {
                const float d0 = bf_lo(w[i]) - mu, d1 = bf_hi(w[i]) - mu;
                sq += d0 * d0 + d1 * d1;
            }
            float mu_b, den;
            ln_scalars(mu, warp_sum(sq) * (1.f / 512.f), mu_b, den);
            const float xn = bf_round(bf_lo(xk) - mu_b) / den;
#pragma unroll
            for (int j = 0; j < 4; j++) { acc[j][0] = acc[j][1] = acc[j][2] = acc[j][3] = 0.f; }
            asm volatile("barrier.cluster.wait.acquire.aligned;" ::: "memory");
#pragma unroll
            for (int i = 0; i < 2; i++) {
                const int r0 = 16 * i + (g & ~1);
                uint2 pw;
                pw.x = pack_bf16(__shfl_sync(0xffffffffu, xn, r0), __shfl_sync(0xffffffffu, xn, r0 + 8));
                pw.y = pack_bf16(__shfl_sync(0xffffffffu, xn, r0 + 1), __shfl_sync(0xffffffffu, xn, r0 + 9));
                mbar_wait(bar_full + 8 * i, 0);
                weighted_rows(acc, voff + i * TILE_BYTES, pw, ds0, ds1);
                __syncwarp();
                if (lane == 0) mbar_arrive(bar_empty + 8 * i);
            }
            store_rows();
            bar_sync(1, 256);
            const int d = tid >> 1, half = tid & 1;
            const float* r = reinterpret_cast<const float*>(smem + SM_R) + half * 16 * 136 + d;
            float a0 = 0.f, a1 = 0.f;
#pragma unroll
            for (int i = 0; i < 8; i++) { a0 += r[(2 * i) * 136]; a1 += r[(2 * i + 1) * 136]; }
            float a = a0 + a1;
            a += __shfl_xor_sync(0xffffffffu, a, 1);
            if (half == 0) st_async_f32(mapa(sb + SM_QP + d * 4, s ^ 1), a, mapa(bar_q, s ^ 1));
            mbar_wait(bar_q, 0);
            if (half == 0) {
                a += reinterpret_cast<const float*>(smem + SM_QP)[d];
                reinterpret_cast<__nv_bfloat16*>(smem + SM_QS)[d] = __float2bfloat16_rn(a);
            }
            bar_sync(1, 256);
        }
        int st = N_K0 % NSTAGES, ph = (N_K0 / NSTAGES) & 1;
        {
            uint4 qf[4];
#pragma unroll
            for (int i = 0; i < 4; i++) qf[i] = lds128(sb + SM_QS + (4 * (i ^ (g & 1)) + t) * 16);
            const uint32_t koff = sb + SM_RING + (16 * warp + g) * 256 + t * 16;
            const uint32_t sw = (g & 1) * 64;
#pragma unroll 1
            for (int i = 0; i < NTILES; i++) {
                mbar_wait(bar_full + 8 * st, ph);
                const uint32_t a0 = koff + st * TILE_BYTES;
                uint4 l0[4], l1[4];
#pragma unroll
                for (int k = 0; k < 4; k++) {
                    l0[k] = lds128(a0 + ((k * 64) ^ sw));
                    l1[k] = lds128(a0 + 2048 + ((k * 64) ^ sw));
                }
                float cA[4] = {0.f, 0.f, 0.f, 0.f}, cB[4] = {0.f, 0.f, 0.f, 0.f};
#pragma unroll
                for (int k = 0; k < 4; k++) {
                    mma16816(cA, l0[k].x, l1[k].x, l0[k].y, l1[k].y, qf[k].x, qf[k].y);
                    mma16816(cB, l0[k].z, l1[k].z, l0[k].w, l1[k].w, qf[k].z, qf[k].w);
                }
                __syncwarp();
                if (lane == 0) mbar_arrive(bar_empty + 8 * st);
                const float s_lo = (g & 1) ? cA[1] + cB[1] : cA[0] + cB[0];
                const float s_hi = (g & 1) ? cA[3] + cB[3] : cA[2] + cB[2];
                const uint32_t s1 = pack_bf16(s_lo, s_hi);
                const uint32_t s2 = pack_bf16(bf_lo(s1) * 0.08838834764831845f, bf_hi(s1) * 0.08838834764831845f);
                if (t == 0) reinterpret_cast<float2*>(smem + SM_S)[(warp * 16 + i) * 8 + g] = make_float2(bf_lo(s2), bf_hi(s2));
                if (++st == NSTAGES) { st = 0; ph ^= 1; }
            }
        }
        {
            __syncwarp();
            const float4* sp = reinterpret_cast<const float4*>(smem + SM_S) + warp * 64 + lane * 2;
            const float4 v0 = sp[0], v1 = sp[1];
            float m = fmaxf(fmaxf(fmaxf(v0.x, v0.y), fmaxf(v0.z, v0.w)), fmaxf(fmaxf(v1.x, v1.y), fmaxf(v1.z, v1.w)));
#pragma unroll
            for (int o = 16; o > 0; o >>= 1) m = fmaxf(m, __shfl_xor_sync(0xffffffffu, m, o));
            const float c = 1.4426950408889634f;
            const float mc = m * c;
            const float p0 = exp2f(fmaf(v0.x, c, -mc)), p1 = exp2f(fmaf(v0.y, c, -mc));
            const float p2 = exp2f(fmaf(v0.z, c, -mc)), p3 = exp2f(fmaf(v0.w, c, -mc));
            const float p4 = exp2f(fmaf(v1.x, c, -mc)), p5 = exp2f(fmaf(v1.y, c, -mc));
            const float p6 = exp2f(fmaf(v1.z, c, -mc)), p7 = exp2f(fmaf(v1.w, c, -mc));
            const float l = warp_sum(((p0 + p1) + (p2 + p3)) + ((p4 + p5) + (p6 + p7)));
            reinterpret_cast<uint4*>(smem + SM_P)[warp * 32 + lane] =
                make_uint4(pack_bf16(p0, p1), pack_bf16(p2, p3), pack_bf16(p4, p5), pack_bf16(p6, p7));
            if (lane == 0) {
                reinterpret_cast<float2*>(smem + SM_ML)[warp] = make_float2(mc, l);
                mbar_arrive(bar_ml);
            }
            __syncwarp();
        }
#pragma unroll
        for (int j = 0; j < 4; j++) { acc[j][0] = acc[j][1] = acc[j][2] = acc[j][3] = 0.f; }
        {
            const uint32_t poff = sb + SM_P + (warp * 128 + (g & ~1)) * 4;
#pragma unroll 1
            for (int i = 0; i < NTILES; i++) {
                st += (i == WO_POS ? 2 : 0) + (i == GU_POS ? 1 : 0);
                if (st >= NSTAGES) { st -= NSTAGES; ph ^= 1; }
                const uint2 pp = lds64(poff + i * 32);
                mbar_wait(bar_full + 8 * st, ph);
                weighted_rows(acc, voff + st * TILE_BYTES, pp, ds0, ds1);
                __syncwarp();
                if (lane == 0) mbar_arrive(bar_empty + 8 * st);
                if (++st == NSTAGES) { st = 0; ph ^= 1; }
            }
            store_rows();
        }
        o_merge();
        bar_arrive(6, NTHREADS);
        if (!ffn) return;
        uint2 dn[8];
        const uint32_t da = sb + SM_RING + (N_DN % NSTAGES) * TILE_BYTES + 4 * t * 1024 + 128 * warp + 8 * g;
        mbar_wait(bar_dn, 0);
#pragma unroll
        for (int k = 0; k < 4; k++) {
            dn[k] = lds64(da + k * 1024);
            dn[4 + k] = lds64(da + k * 1024 + 64);
        }
        uint32_t* yb = sc->yx[ld_epoch(smem) & 1u];
        uint32_t* yp = yb + cta * 1024 + (t & 1) * 512 + 64 * warp + 4 * g;
        const uint32_t fa = sb + SM_R + lane * 48, fc = sb + SM_R + (64 + (lane & 15)) * 48;
        const uint32_t fs = sb + SM_R + (96 + 2 * (lane >> 4)) * 48;
        bar_sync(3, NTHREADS);
        {
            float v[6];
            const uint32_t ad[6] = {fs, fs + 48, fa, fc, fa + 32 * 48, fc + 16 * 48};
            uint4 lo[6], hi[6];
#pragma unroll
            for (int i = 0; i < 6; i++) { lo[i] = lds128(ad[i]); hi[i] = lds128(ad[i] + 16); }
#pragma unroll
            for (int i = 0; i < 6; i++)
                v[i] = ((__uint_as_float(lo[i].x) + __uint_as_float(lo[i].y)) + (__uint_as_float(lo[i].z) + __uint_as_float(lo[i].w))) +
                       ((__uint_as_float(hi[i].x) + __uint_as_float(hi[i].y)) + (__uint_as_float(hi[i].z) + __uint_as_float(hi[i].w)));
            const float mean = v[0] * (1.f / 512.f);
            float mu, den;
            ln_scalars(mean, fmaxf(fmaf(-mean, mean, v[1] * (1.f / 512.f)), 0.f), mu, den);
            const float rs = rcp_fast(den);
            const float gv = bf_round(fmaf(-mu, v[3], v[2]) * rs);
            const float uv = bf_round(fmaf(-mu, v[5], v[4]) * rs);
            const float act = bf_round(gv * rcp_fast(1.f + __expf(-gv))) * uv;
            const int src = ((g >> 1) & 1) * 16 + 4 * t;
            const float a0 = __shfl_sync(0xffffffffu, act, src), a1 = __shfl_sync(0xffffffffu, act, src + 1);
            const float a2 = __shfl_sync(0xffffffffu, act, src + 2), a3 = __shfl_sync(0xffffffffu, act, src + 3);
            const uint32_t awx = pack_bf16(a0, a1), awy = pack_bf16(a2, a3);
            const uint32_t s0 = g < 4 ? sel_lo_e : 0x4444u, q1 = g < 4 ? sel_hi_e : 0x4444u;
            const uint32_t b00 = __byte_perm(awx, 0, s0), b01 = __byte_perm(awx, 0, q1);
            const uint32_t b10 = __byte_perm(awy, 0, s0), b11 = __byte_perm(awy, 0, q1);
            float c[2][2][4];
#pragma unroll
            for (int cb = 0; cb < 2; cb++) {
#pragma unroll
                for (int j = 0; j < 4; j++) c[cb][0][j] = c[cb][1][j] = 0.f;
                mma16816(c[cb][0], dn[4 * cb].x, dn[4 * cb].y, dn[4 * cb + 1].x, dn[4 * cb + 1].y, b00, b01);
                mma16816(c[cb][1], dn[4 * cb + 2].x, dn[4 * cb + 2].y, dn[4 * cb + 3].x, dn[4 * cb + 3].y, b10, b11);
            }
            if (t < 2) {
#pragma unroll
                for (int cb = 0; cb < 2; cb++)
                    st_gpu128(yp + 32 * cb, nz_bits(c[cb][0][0] + c[cb][1][0]), nz_bits(c[cb][0][1] + c[cb][1][1]),
                              nz_bits(c[cb][0][2] + c[cb][1][2]), nz_bits(c[cb][0][3] + c[cb][1][3]));
            }
        }
        if (cta >= 32) return;
        float y0 = 0.f, y1 = 0.f, y2 = 0.f, y3 = 0.f;
        const int pg = tid >> 3;
        if (pg < 29) {
            const uint32_t* p = yb + pg * 3072 + 32 * cta + 4 * (tid & 7);
            const int np = (pg == 28) ? 2 : 3;
            uint4 v[3];
            unsigned n = 0;
            for (;;) {
                bool ok = true;
#pragma unroll
                for (int j = 0; j < 3; j++)
                    if (j < np) v[j] = ld_gpu128(p + j * 1024);
#pragma unroll
                for (int j = 0; j < 3; j++)
                    if (j < np) ok = ok && v[j].x && v[j].y && v[j].z && v[j].w;
                if (ok) break;
                if (++n > SPIN_LIMIT) __trap();
            }
#pragma unroll
            for (int j = 0; j < 3; j++)
                if (j < np) {
                    y0 += __uint_as_float(v[j].x);
                    y1 += __uint_as_float(v[j].y);
                    y2 += __uint_as_float(v[j].z);
                    y3 += __uint_as_float(v[j].w);
                }
        }
        __syncwarp();
#pragma unroll
        for (int o = 8; o <= 16; o <<= 1) {
            y0 += __shfl_xor_sync(0xffffffffu, y0, o);
            y1 += __shfl_xor_sync(0xffffffffu, y1, o);
            y2 += __shfl_xor_sync(0xffffffffu, y2, o);
            y3 += __shfl_xor_sync(0xffffffffu, y3, o);
        }
        if (lane < 8) reinterpret_cast<float4*>(smem + SM_YR)[warp * 8 + lane] = make_float4(y0, y1, y2, y3);
        bar_arrive(5, 288);
    } else {
        const int wi = warp - 8;
        uint2 wof[32];
        uint2 gu[16];
        auto pull_wo = [&]() {
            mbar_wait(bar_wo, 0);
            const int sw = (N_WO + (wi >> 2)) % NSTAGES;
            const uint32_t a = sb + SM_RING + sw * TILE_BYTES + (wi & 3) * 8192 + t * 64 + g * 8;
#pragma unroll
            for (int k = 0; k < 32; k++) wof[k] = lds64(a + k * 256);
            __syncwarp();
            if (lane == 0) {
                mbar_arrive(bar_empty + 8 * (N_WO % NSTAGES));
                mbar_arrive(bar_empty + 8 * ((N_WO + 1) % NSTAGES));
            }
        };
        auto pull_gu = [&]() {
            if (ffn) {
                mbar_wait(bar_gu, 0);
                const uint32_t a = sb + SM_RING + (N_GU % NSTAGES) * TILE_BYTES + wi * 2048 + t * 32 + g * 4;
#pragma unroll
                for (int k = 0; k < 16; k++) {
                    gu[k].x = lds32(a + k * 128);
                    gu[k].y = lds32(a + k * 128 + 16384);
                }
            }
            __syncwarp();
            if (lane == 0) mbar_arrive(bar_empty + 8 * (N_GU % NSTAGES));
        };
        if (warp >= 10) {
            const int i = tid - 320;
            if (i < 128) reinterpret_cast<uint4*>(smem + SM_X)[i] = ldg128(x + i * 8);
            else reinterpret_cast<uint4*>(smem + SM_WR)[i - 128] = ldg128(w_r + (i - 128) * 8);
        }
        asm volatile("barrier.cluster.wait.acquire.aligned;" ::: "memory");
        if (warp == 8) {
            const char* vbase = reinterpret_cast<const char*>(vc + kv_off);
            int st = INIT_TILES % NSTAGES, ph = (INIT_TILES / NSTAGES) & 1;
            int sl = INIT_TILES - DEPTH, pl = 0;
            if (lane < 3) {
                const CUtensorMap* tm = lane == 0 ? &tm_wo : (lane == 1 ? &tm_gate : &tm_up);
                asm volatile("prefetch.tensormap [%0];" ::"l"(tm) : "memory");
            }
            auto produce = [&](int n_begin, int n_end) {
#pragma unroll 1
                for (int n = n_begin; n < n_end; n++) {
                    mbar_wait(bar_full + 8 * sl, pl);
                    if (++sl == NSTAGES) { sl = 0; pl ^= 1; }
                    if (n >= NSTAGES) mbar_wait(bar_empty + 8 * st, ph ^ 1);
                    if (lane == 0) {
                        const uint32_t dst = sb + SM_RING + st * TILE_BYTES, fb = bar_full + 8 * st;
                        if (n == N_WO || n == N_WO + 1) {
                            tma_4d(dst, &tm_wo, 0, 4 * h, 0, 8 * s + 4 * (n - N_WO), bar_wo);
                            mbar_arrive(fb);
                        } else if (n == N_GU) {
                            if (ffn) {
                                tma_5d0(dst, &tm_gate, 16 * cta, bar_gu);
                                tma_5d0(dst + 16384, &tm_up, 16 * cta, bar_gu);
                            }
                            mbar_arrive(fb);
                        } else if (n == N_DN) {
                            if (ffn) bulk_load(dst, w_down + (size_t)cta * 8192, TILE_BYTES / 2, bar_dn, pol);
                        } else {
                            const int j = n - N_V0 - (n > N_WO ? 2 : 0) - (n > N_GU ? 1 : 0);
                            const char* src = (n < N_V0) ? kbase + (size_t)(n - N_K0) * TSTRIDE
                                                         : vbase + (size_t)j * TSTRIDE;
                            mbar_expect_tx(fb, TILE_BYTES);
                            bulk_load(dst, src, TILE_BYTES, fb, pol);
                        }
                    }
                    __syncwarp();
                    if (++st == NSTAGES) { st = 0; ph ^= 1; }
                }
            };
            constexpr int P1 = N_WO + 1 + DEPTH < N_TOT ? N_WO + 1 + DEPTH : N_TOT;
            constexpr int P2 = (GU_POS < 16 && N_GU + DEPTH > P1) ? (N_GU + DEPTH < N_TOT ? N_GU + DEPTH : N_TOT) : P1;
            produce(INIT_TILES, P1);
            if (!WO_LATE) pull_wo();
            produce(P1, P2);
            if (GU_POS < 16) pull_gu();
            produce(P2, N_TOT);
        } else {
            if (ffn) {
                for (int i = tid - 288; i < 512; i += 224) st_gpu128(&sc->yx[i >> 8][cta * 1024 + 4 * (i & 255)], 0u, 0u, 0u, 0u);
            }
            if (warp == 9) {
                unsigned e;
                asm volatile("ld.relaxed.gpu.global.u32 %0, [%1];" : "=r"(e) : "l"(sc->epoch) : "memory");
                if (lane == 0) *reinterpret_cast<unsigned*>(smem + SM_EPOCH) = e;
                if (lane < 8) sc->hacc[(e & 1u) ^ 1u][cta * 8 + lane] = make_float2(0.f, 0.f);
                mbar_wait(bar_ml, 0);
                const float2 ml = reinterpret_cast<const float2*>(smem + SM_ML)[lane & 7];
                float m = ml.x;
#pragma unroll
                for (int o = 4; o > 0; o >>= 1) m = fmaxf(m, __shfl_xor_sync(0xffffffffu, m, o));
                float l = ml.y * exp2f(ml.x - m);
#pragma unroll
                for (int o = 4; o > 0; o >>= 1) l += __shfl_xor_sync(0xffffffffu, l, o);
                if (lane < 2) st_async_f32(mapa(sb + SM_MLX + lane * 4, s ^ 1), lane ? l : m, mapa(bar_mlx, s ^ 1));
                mbar_wait(bar_mlx, 0);
                const float2 ml2 = *reinterpret_cast<const float2*>(smem + SM_MLX);
                const float M = fmaxf(m, ml2.x);
                const float L = l * exp2f(m - M) + ml2.y * exp2f(ml2.x - M);
                if (lane < 8) reinterpret_cast<float*>(smem + SM_F)[lane] = exp2f(ml.x - M) / L;
            }
            if (!WO_LATE) pull_wo();
            if (GU_POS < 16) pull_gu();
        }
        o_merge();
        if (WO_LATE) pull_wo();
        const unsigned epoch = ld_epoch(smem);
        float2* hacc = sc->hacc[epoch & 1u];
        float2* hp = hacc + b * 512 + 256 * s + 32 * wi + 4 * g + 2 * t;
        bar_sync(6 + ((uint32_t)(uintptr_t)hp == 1u), NTHREADS);
        {
            const uint32_t s0 = g < 2 ? sel_lo_e : 0x4444u, s1 = g < 2 ? sel_hi_e : 0x4444u;
            float c[4][4];
#pragma unroll
            for (int j = 0; j < 4; j++) { c[j][0] = c[j][1] = c[j][2] = c[j][3] = 0.f; }
            uint4 ow[4];
#pragma unroll
            for (int q4 = 0; q4 < 4; q4++) ow[q4] = lds128(sb + SM_OBF + t * 64 + q4 * 16);
#pragma unroll
            for (int q4 = 0; q4 < 4; q4++) {
                const uint32_t w4[4] = {ow[q4].x, ow[q4].y, ow[q4].z, ow[q4].w};
#pragma unroll
                for (int j = 0; j < 4; j++) {
                    const int kg = q4 * 4 + j;
                    mma16816(c[j], wof[2 * kg].x, wof[2 * kg].y, wof[2 * kg + 1].x, wof[2 * kg + 1].y,
                             __byte_perm(w4[j], 0, s0), __byte_perm(w4[j], 0, s1));
                }
            }
            const float r0 = (c[0][0] + c[1][0]) + (c[2][0] + c[3][0]);
            const float r1 = (c[0][1] + c[1][1]) + (c[2][1] + c[3][1]);
            const float r2 = __shfl_sync(0xffffffffu, (c[0][2] + c[1][2]) + (c[2][2] + c[3][2]), lane & ~3);
            const float r3 = __shfl_sync(0xffffffffu, (c[0][3] + c[1][3]) + (c[2][3] + c[3][3]), lane & ~3);
            if (t < 2)
                asm volatile("red.relaxed.gpu.global.add.v4.f32 [%0], {%1, %2, %3, %2};" ::"l"(hp), "f"(t ? r2 : r0), "f"(1.0f),
                             "f"(t ? r3 : r1)
                             : "memory");
            __syncwarp();
            if (lane == 0)
                asm volatile("red.relaxed.gpu.global.add.u32 [%0], 1;" ::"l"(sc->counter + (4 * s + (wi >> 1)) * 32) : "memory");
        }
        if (!ffn) return;
        if (GU_POS == 16) pull_gu();
        const float2* hrd = hacc + 64 * wi + 2 * lane;
        const uint32_t xa = sb + SM_X + (64 * wi + 2 * lane) * 2;
        const uint32_t xw0 = lds32(xa), xw1 = lds32(xa + 1024);
        {
            const unsigned target = (epoch + 1u) * 128u;
            unsigned v, n = 0;
            for (;;) {
                asm volatile("ld.relaxed.gpu.global.u32 %0, [%1];" : "=r"(v) : "l"(sc->counter + wi * 32) : "memory");
                if (target - v <= HINT_SLACK) break;
                if (++n > SPIN_LIMIT) __trap();
            }
        }
        uint32_t w8[8];
        {
            float4 a0, a1;
            unsigned n = 0;
            for (;;) {
                asm volatile("ld.relaxed.gpu.global.v4.f32 {%0, %1, %2, %3}, [%4];"
                             : "=f"(a0.x), "=f"(a0.y), "=f"(a0.z), "=f"(a0.w)
                             : "l"(hrd)
                             : "memory");
                asm volatile("ld.relaxed.gpu.global.v4.f32 {%0, %1, %2, %3}, [%4];"
                             : "=f"(a1.x), "=f"(a1.y), "=f"(a1.z), "=f"(a1.w)
                             : "l"(hrd + 512)
                             : "memory");
                if (__all_sync(0xffffffffu, a0.y == 32.f && a0.w == 32.f && a1.y == 32.f && a1.w == 32.f)) break;
                if (++n > SPIN_LIMIT) __trap();
            }
            const uint32_t r0 = pack_bf16(a0.x, a0.z), r1 = pack_bf16(a1.x, a1.z);
            uint32_t* hq = reinterpret_cast<uint32_t*>(smem + SM_HBF) + 32 * wi + lane;
            hq[0] = pack_bf16(bf_lo(xw0) + bf_lo(r0), bf_hi(xw0) + bf_hi(r0));
            hq[256] = pack_bf16(bf_lo(xw1) + bf_lo(r1), bf_hi(xw1) + bf_hi(r1));
            __syncwarp();
            const uint32_t ha = sb + SM_HBF + ((g >> 1) & 1) * 1024 + (64 * wi + 2 * t) * 2;
#pragma unroll
            for (int m = 0; m < 8; m++) w8[m] = lds32(ha + m * 16);
        }
        float* fr = reinterpret_cast<float*>(smem + SM_R) + wi;
        {
            const uint32_t one = (g == 4) ? 0x00003F80u : ((g == 5) ? 0x3F800000u : 0u);
            float c[4][4];
#pragma unroll
            for (int j = 0; j < 4; j++) { c[j][0] = c[j][1] = c[j][2] = c[j][3] = 0.f; }
#pragma unroll
            for (int m = 0; m < 8; m++) {
                const uint32_t b0 = g < 4 ? __byte_perm(w8[m], 0, sel_lo_e) : one;
                const uint32_t b1 = g < 4 ? __byte_perm(w8[m], 0, sel_hi_e) : one;
                mma16816(c[m & 3], gu[2 * m].x, gu[2 * m].y, gu[2 * m + 1].x, gu[2 * m + 1].y, b0, b1);
            }
            if (t < 3) {
                float* p0 = fr + ((t < 2 ? 16 * t : 64) + 2 * g) * 12;
                float* p1 = p0 + (t < 2 ? 32 : 16) * 12;
                p0[0] = (c[0][0] + c[1][0]) + (c[2][0] + c[3][0]);
                p0[12] = (c[0][1] + c[1][1]) + (c[2][1] + c[3][1]);
                p1[0] = (c[0][2] + c[1][2]) + (c[2][2] + c[3][2]);
                p1[12] = (c[0][3] + c[1][3]) + (c[2][3] + c[3][3]);
            }
        }
        float s1a = 0.f, s1b = 0.f, s2a = 0.f, s2b = 0.f;
#pragma unroll
        for (int m = 0; m < 8; m++) {
            const float h0 = bf_lo(w8[m]), h1 = bf_hi(w8[m]);
            s1a += h0;
            s1b += h1;
            s2a = fmaf(h0, h0, s2a);
            s2b = fmaf(h1, h1, s2b);
        }
        float s1 = s1a + s1b, s2 = s2a + s2b;
        s1 += __shfl_xor_sync(0xffffffffu, s1, 1);
        s2 += __shfl_xor_sync(0xffffffffu, s2, 1);
        s1 += __shfl_xor_sync(0xffffffffu, s1, 2);
        s2 += __shfl_xor_sync(0xffffffffu, s2, 2);
        if (lane == 0 || lane == 8) {
            fr[(96 + (lane >> 2)) * 12] = s1;
            fr[(97 + (lane >> 2)) * 12] = s2;
        }
        if (warp == 15 && cta < 32) {
            bar_sync(3, NTHREADS);
            const int ob = cta >> 4;
            const uint32_t fs = sb + SM_R + (96 + 2 * ob) * 48;
            const uint4 a0 = lds128(fs), a1 = lds128(fs + 16), b0 = lds128(fs + 48), b1 = lds128(fs + 64);
            const float mean = (((__uint_as_float(a0.x) + __uint_as_float(a0.y)) + (__uint_as_float(a0.z) + __uint_as_float(a0.w))) +
                                ((__uint_as_float(a1.x) + __uint_as_float(a1.y)) + (__uint_as_float(a1.z) + __uint_as_float(a1.w)))) *
                               (1.f / 512.f);
            const float msq = (((__uint_as_float(b0.x) + __uint_as_float(b0.y)) + (__uint_as_float(b0.z) + __uint_as_float(b0.w))) +
                               ((__uint_as_float(b1.x) + __uint_as_float(b1.y)) + (__uint_as_float(b1.z) + __uint_as_float(b1.w)))) *
                              (1.f / 512.f);
            float mu, den;
            ln_scalars(mean, fmaxf(fmaf(-mean, mean, msq), 0.f), mu, den);
            const float rs = rcp_fast(den);
            const uint4 h0 = lds128(sb + SM_HBF + ob * 1024 + lane * 32);
            const uint4 h1 = lds128(sb + SM_HBF + ob * 1024 + lane * 32 + 16);
            const uint32_t hw[8] = {h0.x, h0.y, h0.z, h0.w, h1.x, h1.y, h1.z, h1.w};
            const uint4 w0 = lds128(sb + SM_WR + lane * 32), w1 = lds128(sb + SM_WR + lane * 32 + 16);
            const uint32_t ww[8] = {w0.x, w0.y, w0.z, w0.w, w1.x, w1.y, w1.z, w1.w};
            float r = 0.f;
#pragma unroll
            for (int i = 0; i < 8; i++) {
                const uint32_t d2 = pack_bf16(bf_lo(hw[i]) - mu, bf_hi(hw[i]) - mu);
                const uint32_t hn2 = pack_bf16(bf_lo(d2) * rs, bf_hi(d2) * rs);
                r = fmaf(bf_lo(hn2), bf_lo(ww[i]), r);
                r = fmaf(bf_hi(hn2), bf_hi(ww[i]), r);
            }
            r = bf_round(warp_sum(r));
            const float sig = bf_round(rcp_fast(1.f + __expf(-r)));
            const float hv = __bfloat162float(reinterpret_cast<const __nv_bfloat16*>(smem + SM_HBF)[32 * cta + lane]);
            const float hn = bf_round(bf_round(hv - mu) * rs);
            if (cta == 0 && lane == 0) sc->epoch[0] = epoch + 1u;
            bar_sync(5 + (sig > 2.f), 288);
            const float* yr = reinterpret_cast<const float*>(smem + SM_YR) + lane;
            const float y = ((yr[0] + yr[32]) + (yr[64] + yr[96])) + ((yr[128] + yr[160]) + (yr[192] + yr[224]));
            const float upd = bf_round(bf_round(y) * sig);
            out[32 * cta + lane] = __float2bfloat16_rn(hv + bf_round(hn + upd));
        } else {
            bar_arrive(3, NTHREADS);
        }
    }
}

typedef CUresult (*EncodeTiledFn)(CUtensorMap*, CUtensorMapDataType, cuuint32_t, void*, const cuuint64_t*, const cuuint64_t*,
                                  const cuuint32_t*, const cuuint32_t*, CUtensorMapInterleave, CUtensorMapSwizzle,
                                  CUtensorMapL2promotion, CUtensorMapFloatOOBfill);

}

extern "C" void kernel_launch(void* const* d_in, const int* in_sizes, int n_in, void* d_out, int out_size) {
    (void)in_sizes; (void)n_in; (void)out_size;
    const __nv_bfloat16* x = (const __nv_bfloat16*)d_in[0];
    const __nv_bfloat16* kc = (const __nv_bfloat16*)d_in[1];
    const __nv_bfloat16* vc = (const __nv_bfloat16*)d_in[2];
    const __nv_bfloat16* w_r = (const __nv_bfloat16*)d_in[6];
    const __nv_bfloat16* w_down = (const __nv_bfloat16*)d_in[9];

    void* fn = nullptr;
    cudaDriverEntryPointQueryResult qres;
    cudaGetDriverEntryPoint("cuTensorMapEncodeTiled", &fn, cudaEnableDefault, &qres);
    if (fn == nullptr) return;
    EncodeTiledFn encode = (EncodeTiledFn)fn;
    CUtensorMap tm_wq, tm_wo, tm_gate, tm_up;
    const cuuint32_t ones[5] = {1, 1, 1, 1, 1};
    {
        const cuuint64_t dims[2] = {4096, 512}, strides[1] = {8192};
        const cuuint32_t box[2] = {128, 128};
        encode(&tm_wq, CU_TENSOR_MAP_DATA_TYPE_BFLOAT16, 2, d_in[3], dims, strides, box, ones, CU_TENSOR_MAP_INTERLEAVE_NONE,
               CU_TENSOR_MAP_SWIZZLE_NONE, CU_TENSOR_MAP_L2_PROMOTION_L2_256B, CU_TENSOR_MAP_FLOAT_OOB_FILL_NONE);
    }
    {
        const cuuint64_t dims[4] = {32, 128, 32, 16}, strides[3] = {32 * 1024, 1024, 64};
        const cuuint32_t box[4] = {32, 4, 32, 4};
        encode(&tm_wo, CU_TENSOR_MAP_DATA_TYPE_BFLOAT16, 4, d_in[4], dims, strides, box, ones, CU_TENSOR_MAP_INTERLEAVE_NONE,
               CU_TENSOR_MAP_SWIZZLE_NONE, CU_TENSOR_MAP_L2_PROMOTION_L2_128B, CU_TENSOR_MAP_FLOAT_OOB_FILL_NONE);
    }
    for (int i = 0; i < 2; i++) {
        const cuuint64_t dims[5] = {FF, 4, 2, 8, 8}, strides[4] = {2 * FF * 2, FF * 2, 8 * FF * 2, 64 * FF * 2};
        const cuuint32_t box[5] = {16, 4, 2, 8, 8};
        encode(i ? &tm_up : &tm_gate, CU_TENSOR_MAP_DATA_TYPE_BFLOAT16, 5, d_in[7 + i], dims, strides, box, ones,
               CU_TENSOR_MAP_INTERLEAVE_NONE, CU_TENSOR_MAP_SWIZZLE_NONE, CU_TENSOR_MAP_L2_PROMOTION_L2_128B,
               CU_TENSOR_MAP_FLOAT_OOB_FILL_NONE);
    }
    void* sc = nullptr;
    cudaGetSymbolAddress(&sc, g_scratch);
    cudaFuncSetAttribute(fused_decode_kernel, cudaFuncAttributeMaxDynamicSharedMemorySize, SM_TOTAL);
    fused_decode_kernel<<<NCTA, NTHREADS, SM_TOTAL>>>(tm_wq, tm_wo, tm_gate, tm_up, x, kc, vc, w_r, w_down,
                                                      (__nv_bfloat16*)d_out, (Scratch*)sc);
}
```
